```python
import torch

def _softmax(x, axis=-1):
    return torch.softmax(x, dim=axis)
def _gelu(x):
    return torch.nn.functional.gelu(x, approximate="tanh")
def _silu(x):
    return torch.nn.functional.silu(x)
def _sigmoid(x):
    return torch.sigmoid(x)
def _layernorm(x, axis=-1, eps=1e-5):
    m = x.mean(dim=axis, keepdim=True)
    v = x.var(dim=axis, keepdim=True, unbiased=False)
    return (x - m) / torch.sqrt(v + eps)
def _scatter_add(tgt, idx, src, axis=0):
    return tgt.clone().index_add_(axis, idx, src)
def _segment_sum(src, seg, n):
    out = torch.zeros((n,) + src.shape[1:], dtype=src.dtype)
    return out.index_add_(0, seg, src)
def _pad(x, pw):
    flat = tuple(v for pair in reversed(pw) for v in pair)
    return torch.nn.functional.pad(x, flat)

kernel_name = 'gated_mix__ssm_conv_s4d__glu_gated_reglu__prompt'

def setup_inputs():

    _w = (lambda a: (lambda t: t.to(torch.bfloat16) if t.is_floating_point() else t)(torch.as_tensor(a)))
    def _A_setup():
        Bsz, L, D, N = 1, 2048, 512, 128
        return {
            "u": _w((lambda *s: torch.randn(*s, dtype=torch.bfloat16) * 0.05)(Bsz, L, D)),
            "log_A_real": _w((lambda *s: torch.randn(*s, dtype=torch.bfloat16) * 3.2)(D, N) * 0.5),
            "A_imag": _w((lambda *s: torch.randn(*s, dtype=torch.bfloat16) * 0.05)(D, N) * 3.14),
            "C_real": _w((lambda *s: torch.randn(*s, dtype=torch.bfloat16) * 0.05)(D, N) / N ** 0.5),
            "C_imag": _w((lambda *s: torch.randn(*s, dtype=torch.bfloat16) * 0.1)(D, N) / N ** 0.5),
            "log_dt": _w((lambda *s: torch.randn(*s, dtype=torch.bfloat16) * 0.05)(D) * 0.5 - 4.0),
            "D_skip": _w((lambda *s: torch.randn(*s, dtype=torch.bfloat16) * 0.05)(D)),
        }
    _A_in = _A_setup()

    def _B_setup():
        B, S, D, F = 1, 2048, 512, 1792
        return {
            "x": _w((lambda *s: torch.randn(*s, dtype=torch.bfloat16) * 0.05)(B, S, D)),
            "W_gate": _w((lambda *s: torch.randn(*s, dtype=torch.bfloat16) * 0.8)(D, F) * (2.0 / D) ** 0.5),
            "W_up": _w((lambda *s: torch.randn(*s, dtype=torch.bfloat16) * 0.8)(D, F) * (2.0 / D) ** 0.5),
            "W_down": _w((lambda *s: torch.randn(*s, dtype=torch.bfloat16) * 0.8)(F, D) * (1.0 / F) ** 0.5),
        }
    _B_in = _B_setup()

    return {
        "A_u": _A_in["u"],
        "A_log_A_real": _A_in["log_A_real"],
        "A_A_imag": _A_in["A_imag"],
        "A_C_real": _A_in["C_real"],
        "A_C_imag": _A_in["C_imag"],
        "A_log_dt": _A_in["log_dt"],
        "A_D_skip": _A_in["D_skip"],
        "B_x": _B_in["x"],
        "B_W_gate": _B_in["W_gate"],
        "B_W_up": _B_in["W_up"],
        "B_W_down": _B_in["W_down"],
        "gate_w": _w((lambda *s: torch.randn(*s, dtype=torch.bfloat16) * 0.05)(512) * 16.0),
    }

def reference(A_u, A_log_A_real, A_A_imag, A_C_real, A_C_imag, A_log_dt, A_D_skip, B_x, B_W_gate, B_W_up, B_W_down, gate_w):
    def _A_ref(u, log_A_real, A_imag, C_real, C_imag, log_dt, D_skip):
        L = u.shape[1]
        dt = torch.exp(log_dt)
        A = -torch.exp(log_A_real) + 1j * A_imag
        C = (C_real + 1j * C_imag) * dt[:, None]
        pos = (lambda x, dt: x.to(dt))(torch.arange(L), log_dt.dtype)
        P = torch.exp((A * dt[:, None])[:, :, None] * pos[None, None, :])
        K = 2.0 * torch.einsum("dn,dnl->dl", C, P).real
        L2 = 2 * L
        u_t = (lambda x, *d: x.permute(*d))(u, 0, 2, 1)
        Kf = (lambda x, *a, **k: torch.fft.rfft(x.float(), *a, **k))(K, L2)
        Uf = (lambda x, *a, **k: torch.fft.rfft(x.float(), *a, **k))(u_t, L2)
        y = (lambda x, *a, **k: torch.fft.irfft(x, *a, **k).to(torch.bfloat16))(Uf * Kf[None, :, :], L2)[:, :, :L]
        y = (lambda x, *d: x.permute(*d))(y, 0, 2, 1)
        return y + u * D_skip[None, None, :]

    def _B_ref(x, W_gate, W_up, W_down):
        gate = torch.einsum("bsd,df->bsf", x, W_gate)
        up = torch.einsum("bsd,df->bsf", x, W_up)
        gate = gate * (lambda x, dt: x.to(dt))(gate > 0, gate.dtype)
        h = gate * up
        return torch.einsum("bsf,fd->bsd", h, W_down)

    x = A_u
    g = _sigmoid((x * gate_w).sum(-1, keepdims=True))
    a = _A_ref(x, A_log_A_real, A_A_imag, A_C_real, A_C_imag, A_log_dt, A_D_skip)
    b = _B_ref(x, B_W_gate, B_W_up, B_W_down)
    return g * a + (1 - g) * b
```

```cpp
#include <cuda_runtime.h>
#include <cuda.h>
#include <cuda_bf16.h>
#include <cuda_fp16.h>
#include <cstdint>
#include <cstring>

typedef __nv_bfloat16 bf16;

constexpr int NP = 4, NS = 6;
constexpr int NSLOT = NP + NS;
constexpr int N2 = 7;
constexpr int SLOT = 16384;
constexpr int CONV_OFF = NSLOT * SLOT;
constexpr int TS = 144;
constexpr int WE4 = 17152, WO4 = 21248, WE8 = 25344, WO8 = 28928, WSS = 32512, CHB = 34560;
constexpr int UST = 1184, KLO = 4736, CHS = 6528;
constexpr int CONV_BYTES = 60672;
#define MIDA -1
#define MIDB 3
#define KUNROLL 4
constexpr int KUNR = KUNROLL;
#define MID2 8
#define ESY 0
#define PSU 400
#define PSA 400
#define PSB 500
#define PS0 700
#define NOUT 4
#define ALD 24
#define XTN 0
constexpr int BAR_OFF = CONV_OFF + CONV_BYTES;
constexpr int SMEM_BYTES = BAR_OFF + 512 + 1024;

struct Scratch {
  bf16 h[2048 * 1792];
  bf16 aT[512 * 2048];
  bf16 uS[512 * 2048];
  bf16 g[2048];
  uint32_t fu[128 * 32];
  uint32_t flag[128 * 32];
  uint32_t epoch[160];
};
__device__ __align__(1024) Scratch g_s;

struct TMap { uint64_t v[16]; };
struct Params {
  const bf16 *logA, *Aim, *Cre, *Cim, *logdt;
  uint64_t sc;
  TMap x, wA, ut, wB, wd, h, out, us;
  const bf16 *u, *Dsk, *gw, *Wd;
};

__device__ __forceinline__ uint32_t s2u(const void* p) { return (uint32_t)__cvta_generic_to_shared(p); }
__device__ __forceinline__ void mbar_init(uint32_t b, uint32_t c) { asm volatile("mbarrier.init.shared::cta.b64 [%0], %1;" ::"r"(b), "r"(c) : "memory"); }
__device__ __forceinline__ void mbar_expect(uint32_t b, uint32_t n) { asm volatile("mbarrier.arrive.expect_tx.shared::cta.b64 _, [%0], %1;" ::"r"(b), "r"(n) : "memory"); }
__device__ __forceinline__ void mbar_arrive(uint32_t b) { asm volatile("mbarrier.arrive.shared::cta.b64 _, [%0];" ::"r"(b) : "memory"); }
__device__ __forceinline__ void mbar_arrive_n(uint32_t b, uint32_t n) { asm volatile("mbarrier.arrive.shared::cta.b64 _, [%0], %1;" ::"r"(b), "r"(n) : "memory"); }
__device__ __forceinline__ void mbar_wait(uint32_t b, uint32_t ph) {
  asm volatile("{\n.reg .pred p, q;\n.reg .u32 c;\nmov.u32 c, 0;\nLW%=:\nmbarrier.try_wait.parity.shared::cta.b64 p, [%0], %1;\n@p bra LD%=;\n"
               "add.u32 c, c, 1;\nsetp.lt.u32 q, c, 1048576;\n@q bra LW%=;\ntrap;\nLD%=:\n}" ::"r"(b), "r"(ph) : "memory");
}
__device__ __forceinline__ bool elect() { uint32_t r; asm volatile("{.reg .pred p; elect.sync _|p, 0xffffffff; selp.u32 %0,1,0,p;}" : "=r"(r)); return r; }
__device__ __forceinline__ void tma2d(uint32_t dst, const TMap* m, int c0, int c1, uint32_t bar) {
  asm volatile("cp.async.bulk.tensor.2d.shared::cluster.global.mbarrier::complete_tx::bytes [%0], [%1, {%3, %4}], [%2];" ::"r"(dst), "l"(m), "r"(bar), "r"(c0), "r"(c1) : "memory");
}
__device__ __forceinline__ void tma4d(uint32_t dst, const TMap* m, int c0, int c1, int c2, int c3, uint32_t bar) {
  asm volatile("cp.async.bulk.tensor.4d.shared::cluster.global.mbarrier::complete_tx::bytes [%0], [%1, {%3, %4, %5, %6}], [%2];" ::"r"(dst), "l"(m), "r"(bar), "r"(c0), "r"(c1), "r"(c2), "r"(c3) : "memory");
}
__device__ __forceinline__ void tma5d(uint32_t dst, const TMap* m, int c0, int c1, int c2, int c3, int c4, uint32_t bar) {
  asm volatile("cp.async.bulk.tensor.5d.shared::cluster.global.mbarrier::complete_tx::bytes [%0], [%1, {%3, %4, %5, %6, %7}], [%2];" ::"r"(dst), "l"(m), "r"(bar), "r"(c0), "r"(c1), "r"(c2), "r"(c3), "r"(c4) : "memory");
}
__device__ __forceinline__ void tma_store4d(const TMap* m, uint32_t src, int c0, int c1, int c2, int c3) {
  asm volatile("cp.async.bulk.tensor.4d.global.shared::cta.bulk_group [%0, {%2, %3, %4, %5}], [%1];" ::"l"(m), "r"(src), "r"(c0), "r"(c1), "r"(c2), "r"(c3) : "memory");
}
__device__ __forceinline__ void prefetch_map(const TMap* m) { asm volatile("prefetch.tensormap [%0];" ::"l"(m) : "memory"); }
__device__ __forceinline__ uint64_t mkdesc(uint32_t addr, uint32_t lbo, uint32_t sbo, uint32_t mode) {
  return (uint64_t)((addr & 0x3FFFF) >> 4) | ((uint64_t)(lbo >> 4) << 16) | ((uint64_t)(sbo >> 4) << 32) | ((uint64_t)mode << 62);
}
__device__ __forceinline__ void wg_fence() { asm volatile("wgmma.fence.sync.aligned;" ::: "memory"); }
__device__ __forceinline__ void wg_commit() { asm volatile("wgmma.commit_group.sync.aligned;" ::: "memory"); }
template <int N> __device__ __forceinline__ void wg_wait() { asm volatile("wgmma.wait_group.sync.aligned %0;" ::"n"(N) : "memory"); }
__device__ __forceinline__ void bar_sync(int id, int n) { asm volatile("bar.sync %0, %1;" ::"r"(id), "r"(n) : "memory"); }
__device__ __forceinline__ void bar_arrive(int id, int n) { asm volatile("bar.arrive %0, %1;" ::"r"(id), "r"(n) : "memory"); }
__device__ __forceinline__ uint32_t ld_acq(const uint32_t* p) { uint32_t v; asm volatile("ld.acquire.gpu.global.u32 %0, [%1];" : "=r"(v) : "l"(p) : "memory"); return v; }
__device__ __forceinline__ uint32_t ld_rlx(const uint32_t* p) { uint32_t v; asm volatile("ld.relaxed.gpu.global.u32 %0, [%1];" : "=r"(v) : "l"(p) : "memory"); return v; }
__device__ __forceinline__ void publish(uint32_t* p, uint32_t v, bool active) {
  asm volatile("fence.proxy.async;" ::: "memory");
  if (active) asm volatile("st.relaxed.gpu.global.u32 [%0], %1;" ::"l"(p), "r"(v) : "memory");
}
__device__ __forceinline__ void st_rel(uint32_t* p, uint32_t v) { asm volatile("st.release.gpu.global.u32 [%0], %1;" ::"l"(p), "r"(v) : "memory"); }
__device__ __forceinline__ uint4 ldg_cg(const void* p) { uint4 v; asm volatile("ld.global.cg.v4.u32 {%0,%1,%2,%3}, [%4];" : "=r"(v.x), "=r"(v.y), "=r"(v.z), "=r"(v.w) : "l"(p) : "memory"); return v; }
__device__ __forceinline__ uint4 ldg_nc(const void* p) { uint4 v; asm volatile("ld.global.nc.v4.u32 {%0,%1,%2,%3}, [%4];" : "=r"(v.x), "=r"(v.y), "=r"(v.z), "=r"(v.w) : "l"(p)); return v; }
__device__ __forceinline__ void stg128(void* p, uint32_t a, uint32_t b, uint32_t c, uint32_t d) { asm volatile("st.global.v4.u32 [%0], {%1,%2,%3,%4};" ::"l"(p), "r"(a), "r"(b), "r"(c), "r"(d) : "memory"); }
__device__ __forceinline__ uint32_t cvt2(float lo, float hi) { uint32_t r; asm("cvt.rn.bf16x2.f32 %0, %1, %2;" : "=r"(r) : "f"(hi), "f"(lo)); return r; }
__device__ __forceinline__ uint32_t cvt2relu(float lo, float hi) { uint32_t r; asm("cvt.rn.relu.bf16x2.f32 %0, %1, %2;" : "=r"(r) : "f"(hi), "f"(lo)); return r; }
__device__ __forceinline__ uint32_t hmul2(uint32_t a, uint32_t b) { uint32_t r; asm("mul.rn.bf16x2 %0, %1, %2;" : "=r"(r) : "r"(a), "r"(b)); return r; }
__device__ __forceinline__ uint32_t hadd2(uint32_t a, uint32_t b) { uint32_t r; asm("add.rn.bf16x2 %0, %1, %2;" : "=r"(r) : "r"(a), "r"(b)); return r; }
__device__ __forceinline__ uint32_t hsub2(uint32_t a, uint32_t b) { uint32_t r; asm("sub.rn.bf16x2 %0, %1, %2;" : "=r"(r) : "r"(a), "r"(b)); return r; }
__device__ __forceinline__ float blo(uint32_t v) { return __uint_as_float(v << 16); }
__device__ __forceinline__ float bhi(uint32_t v) { return __uint_as_float(v & 0xffff0000u); }
__device__ __forceinline__ void stsm4t(uint32_t a, uint32_t r0, uint32_t r1, uint32_t r2, uint32_t r3) {
  asm volatile("stmatrix.sync.aligned.m8n8.x4.trans.shared.b16 [%0], {%1,%2,%3,%4};" ::"r"(a), "r"(r0), "r"(r1), "r"(r2), "r"(r3) : "memory");
}
__device__ __forceinline__ void stsm2t(uint32_t a, uint32_t r0, uint32_t r1) {
  asm volatile("stmatrix.sync.aligned.m8n8.x2.trans.shared.b16 [%0], {%1,%2};" ::"r"(a), "r"(r0), "r"(r1) : "memory");
}
__device__ __forceinline__ void stsm4(uint32_t a, uint32_t r0, uint32_t r1, uint32_t r2, uint32_t r3) {
  asm volatile("stmatrix.sync.aligned.m8n8.x4.shared.b16 [%0], {%1,%2,%3,%4};" ::"r"(a), "r"(r0), "r"(r1), "r"(r2), "r"(r3) : "memory");
}
__device__ __forceinline__ void ldsm4(uint32_t* r, uint32_t a) {
  asm volatile("ldmatrix.sync.aligned.m8n8.x4.shared.b16 {%0,%1,%2,%3}, [%4];" : "=r"(r[0]), "=r"(r[1]), "=r"(r[2]), "=r"(r[3]) : "r"(a) : "memory");
}
__device__ __forceinline__ void ldsm4t(uint32_t* r, uint32_t a) {
  asm volatile("ldmatrix.sync.aligned.m8n8.x4.trans.shared.b16 {%0,%1,%2,%3}, [%4];" : "=r"(r[0]), "=r"(r[1]), "=r"(r[2]), "=r"(r[3]) : "r"(a) : "memory");
}
__device__ __forceinline__ void ldsm2t(uint32_t* r, uint32_t a) {
  asm volatile("ldmatrix.sync.aligned.m8n8.x2.trans.shared.b16 {%0,%1}, [%2];" : "=r"(r[0]), "=r"(r[1]) : "r"(a) : "memory");
}
__device__ __forceinline__ void sts128(uint32_t a, uint32_t x, uint32_t y, uint32_t z, uint32_t w) { asm volatile("st.shared.v4.u32 [%0], {%1,%2,%3,%4};" ::"r"(a), "r"(x), "r"(y), "r"(z), "r"(w) : "memory"); }
__device__ __forceinline__ void sts32(uint32_t a, uint32_t x) { asm volatile("st.shared.u32 [%0], %1;" ::"r"(a), "r"(x) : "memory"); }
__device__ __forceinline__ void sts16(uint32_t a, uint32_t x) { asm volatile("st.shared.u16 [%0], %1;" ::"r"(a), "h"((uint16_t)x) : "memory"); }
__device__ __forceinline__ void lds128(uint32_t* r, uint32_t a) { asm volatile("ld.shared.v4.u32 {%0,%1,%2,%3}, [%4];" : "=r"(r[0]), "=r"(r[1]), "=r"(r[2]), "=r"(r[3]) : "r"(a) : "memory"); }
__device__ __forceinline__ uint32_t lds32(uint32_t a) { uint32_t r; asm volatile("ld.shared.u32 %0, [%1];" : "=r"(r) : "r"(a) : "memory"); return r; }
__device__ __forceinline__ uint2 ldg_nc64(const void* p) { uint2 v; asm volatile("ld.global.nc.v2.u32 {%0,%1}, [%2];" : "=r"(v.x), "=r"(v.y) : "l"(p)); return v; }
__device__ __forceinline__ void fence_async_smem() { asm volatile("fence.proxy.async.shared::cta;" ::: "memory"); }
__device__ __forceinline__ uint32_t cvth2(float lo, float hi) { uint32_t r; asm("cvt.rn.f16x2.f32 %0, %1, %2;" : "=r"(r) : "f"(hi), "f"(lo)); return r; }
__device__ __forceinline__ float bfr(float x) { return __bfloat162float(__float2bfloat16(x)); }
__device__ __forceinline__ float2 cmul(float2 a, float2 b) { return make_float2(fmaf(a.x, b.x, -a.y * b.y), fmaf(a.x, b.y, a.y * b.x)); }
__device__ __forceinline__ float2 cexp2(float a2, float b) {
  float e, sn, cs;
  asm("ex2.approx.ftz.f32 %0, %1;" : "=f"(e) : "f"(a2));
  asm("sin.approx.ftz.f32 %0, %1;" : "=f"(sn) : "f"(b));
  asm("cos.approx.ftz.f32 %0, %1;" : "=f"(cs) : "f"(b));
  return make_float2(e * cs, e * sn);
}
struct HC { uint32_t re, im; };
__device__ __forceinline__ __half2 ash2(uint32_t v) { return *reinterpret_cast<__half2*>(&v); }
__device__ __forceinline__ uint32_t asu(__half2 v) { return *reinterpret_cast<uint32_t*>(&v); }
__device__ __forceinline__ HC hmul(HC a, HC b) {
  return {asu(__hfma2(ash2(a.re), ash2(b.re), __hneg2(__hmul2_rn(ash2(a.im), ash2(b.im))))), asu(__hfma2(ash2(a.re), ash2(b.im), __hmul2_rn(ash2(a.im), ash2(b.re))))};
}
__device__ __forceinline__ HC hmulc(HC a, HC b) {
  return {asu(__hfma2(ash2(a.re), ash2(b.re), __hmul2_rn(ash2(a.im), ash2(b.im)))), asu(__hfma2(ash2(a.im), ash2(b.re), __hneg2(__hmul2_rn(ash2(a.re), ash2(b.im)))))};
}
__device__ __forceinline__ HC cvthc(float2 a, float2 b) { return {cvth2(a.x, b.x), cvth2(a.y, b.y)}; }
__device__ __forceinline__ void stsmc(uint32_t a, HC x, HC y) { stsm4(a, x.re, x.im, y.re, y.im); }
__device__ __forceinline__ float2 csq(float2 a) { return make_float2(fmaf(a.x, a.x, -a.y * a.y), (a.x + a.x) * a.y); }
__device__ __forceinline__ uint32_t cvth2(float2 a) { return cvth2(a.x, a.y); }
__device__ __forceinline__ void stsm2(uint32_t a, uint32_t r0, uint32_t r1) {
  asm volatile("stmatrix.sync.aligned.m8n8.x2.shared.b16 [%0], {%1,%2};" ::"r"(a), "r"(r0), "r"(r1) : "memory");
}
__device__ __forceinline__ uint32_t ldg_nc32(const void* p) { uint32_t v; asm volatile("ld.global.nc.u32 %0, [%1];" : "=r"(v) : "l"(p)); return v; }
__device__ __forceinline__ uint32_t ldg_nc16(const void* p) { uint16_t v; asm volatile("ld.global.nc.u16 %0, [%1];" : "=h"(v) : "l"(p)); return v; }
__device__ __forceinline__ void mma_f16(float* d, uint32_t a0, uint32_t a1, uint32_t a2, uint32_t a3, uint32_t b0, uint32_t b1) {
  asm volatile("mma.sync.aligned.m16n8k16.row.col.f32.f16.f16.f32 {%0,%1,%2,%3}, {%4,%5,%6,%7}, {%8,%9}, {%0,%1,%2,%3};"
               : "+f"(d[0]), "+f"(d[1]), "+f"(d[2]), "+f"(d[3]) : "r"(a0), "r"(a1), "r"(a2), "r"(a3), "r"(b0), "r"(b1));
}
__device__ __forceinline__ void poll_flags(const uint32_t* p, bool active, uint32_t val) {
#pragma unroll 1
  for (int i = 0; i < (1 << 20); i++) {
    uint32_t v = active ? ld_acq(p) : val;
    if (__all_sync(0xffffffffu, v == val)) return;
  }
  __trap();
}
#define TR(i)
#define TG(i)

#define KT(i)
__device__ __forceinline__ void wg_ss128(float* d, uint64_t da, uint64_t db, int sc) {
  asm volatile("{.reg .pred p; setp.ne.b32 p,%66,0; wgmma.mma_async.sync.aligned.m64n128k16.f32.bf16.bf16 {%0,%1,%2,%3,%4,%5,%6,%7,%8,%9,%10,%11,%12,%13,%14,%15,%16,%17,%18,%19,%20,%21,%22,%23,%24,%25,%26,%27,%28,%29,%30,%31,%32,%33,%34,%35,%36,%37,%38,%39,%40,%41,%42,%43,%44,%45,%46,%47,%48,%49,%50,%51,%52,%53,%54,%55,%56,%57,%58,%59,%60,%61,%62,%63},%64,%65,p,1,1,0,1;}"
    : "+f"(d[0]),"+f"(d[1]),"+f"(d[2]),"+f"(d[3]),"+f"(d[4]),"+f"(d[5]),"+f"(d[6]),"+f"(d[7]),"+f"(d[8]),"+f"(d[9]),"+f"(d[10]),"+f"(d[11]),"+f"(d[12]),"+f"(d[13]),"+f"(d[14]),"+f"(d[15]),"+f"(d[16]),"+f"(d[17]),"+f"(d[18]),"+f"(d[19]),"+f"(d[20]),"+f"(d[21]),"+f"(d[22]),"+f"(d[23]),"+f"(d[24]),"+f"(d[25]),"+f"(d[26]),"+f"(d[27]),"+f"(d[28]),"+f"(d[29]),"+f"(d[30]),"+f"(d[31]),"+f"(d[32]),"+f"(d[33]),"+f"(d[34]),"+f"(d[35]),"+f"(d[36]),"+f"(d[37]),"+f"(d[38]),"+f"(d[39]),"+f"(d[40]),"+f"(d[41]),"+f"(d[42]),"+f"(d[43]),"+f"(d[44]),"+f"(d[45]),"+f"(d[46]),"+f"(d[47]),"+f"(d[48]),"+f"(d[49]),"+f"(d[50]),"+f"(d[51]),"+f"(d[52]),"+f"(d[53]),"+f"(d[54]),"+f"(d[55]),"+f"(d[56]),"+f"(d[57]),"+f"(d[58]),"+f"(d[59]),"+f"(d[60]),"+f"(d[61]),"+f"(d[62]),"+f"(d[63])
    : "l"(da),"l"(db),"r"(sc));
}
__device__ __forceinline__ void wg_ss192(float* d, uint64_t da, uint64_t db, int sc) {
  asm volatile("{.reg .pred p; setp.ne.b32 p,%98,0; wgmma.mma_async.sync.aligned.m64n192k16.f32.bf16.bf16 {%0,%1,%2,%3,%4,%5,%6,%7,%8,%9,%10,%11,%12,%13,%14,%15,%16,%17,%18,%19,%20,%21,%22,%23,%24,%25,%26,%27,%28,%29,%30,%31,%32,%33,%34,%35,%36,%37,%38,%39,%40,%41,%42,%43,%44,%45,%46,%47,%48,%49,%50,%51,%52,%53,%54,%55,%56,%57,%58,%59,%60,%61,%62,%63,%64,%65,%66,%67,%68,%69,%70,%71,%72,%73,%74,%75,%76,%77,%78,%79,%80,%81,%82,%83,%84,%85,%86,%87,%88,%89,%90,%91,%92,%93,%94,%95},%96,%97,p,1,1,0,1;}"
    : "+f"(d[0]),"+f"(d[1]),"+f"(d[2]),"+f"(d[3]),"+f"(d[4]),"+f"(d[5]),"+f"(d[6]),"+f"(d[7]),"+f"(d[8]),"+f"(d[9]),"+f"(d[10]),"+f"(d[11]),"+f"(d[12]),"+f"(d[13]),"+f"(d[14]),"+f"(d[15]),"+f"(d[16]),"+f"(d[17]),"+f"(d[18]),"+f"(d[19]),"+f"(d[20]),"+f"(d[21]),"+f"(d[22]),"+f"(d[23]),"+f"(d[24]),"+f"(d[25]),"+f"(d[26]),"+f"(d[27]),"+f"(d[28]),"+f"(d[29]),"+f"(d[30]),"+f"(d[31]),"+f"(d[32]),"+f"(d[33]),"+f"(d[34]),"+f"(d[35]),"+f"(d[36]),"+f"(d[37]),"+f"(d[38]),"+f"(d[39]),"+f"(d[40]),"+f"(d[41]),"+f"(d[42]),"+f"(d[43]),"+f"(d[44]),"+f"(d[45]),"+f"(d[46]),"+f"(d[47]),"+f"(d[48]),"+f"(d[49]),"+f"(d[50]),"+f"(d[51]),"+f"(d[52]),"+f"(d[53]),"+f"(d[54]),"+f"(d[55]),"+f"(d[56]),"+f"(d[57]),"+f"(d[58]),"+f"(d[59]),"+f"(d[60]),"+f"(d[61]),"+f"(d[62]),"+f"(d[63]),"+f"(d[64]),"+f"(d[65]),"+f"(d[66]),"+f"(d[67]),"+f"(d[68]),"+f"(d[69]),"+f"(d[70]),"+f"(d[71]),"+f"(d[72]),"+f"(d[73]),"+f"(d[74]),"+f"(d[75]),"+f"(d[76]),"+f"(d[77]),"+f"(d[78]),"+f"(d[79]),"+f"(d[80]),"+f"(d[81]),"+f"(d[82]),"+f"(d[83]),"+f"(d[84]),"+f"(d[85]),"+f"(d[86]),"+f"(d[87]),"+f"(d[88]),"+f"(d[89]),"+f"(d[90]),"+f"(d[91]),"+f"(d[92]),"+f"(d[93]),"+f"(d[94]),"+f"(d[95])
    : "l"(da),"l"(db),"r"(sc));
}
__device__ __forceinline__ void wg_ss256(float* d, uint64_t da, uint64_t db, int sc) {
  asm volatile("{.reg .pred p; setp.ne.b32 p,%130,0; wgmma.mma_async.sync.aligned.m64n256k16.f32.bf16.bf16 {%0,%1,%2,%3,%4,%5,%6,%7,%8,%9,%10,%11,%12,%13,%14,%15,%16,%17,%18,%19,%20,%21,%22,%23,%24,%25,%26,%27,%28,%29,%30,%31,%32,%33,%34,%35,%36,%37,%38,%39,%40,%41,%42,%43,%44,%45,%46,%47,%48,%49,%50,%51,%52,%53,%54,%55,%56,%57,%58,%59,%60,%61,%62,%63,%64,%65,%66,%67,%68,%69,%70,%71,%72,%73,%74,%75,%76,%77,%78,%79,%80,%81,%82,%83,%84,%85,%86,%87,%88,%89,%90,%91,%92,%93,%94,%95,%96,%97,%98,%99,%100,%101,%102,%103,%104,%105,%106,%107,%108,%109,%110,%111,%112,%113,%114,%115,%116,%117,%118,%119,%120,%121,%122,%123,%124,%125,%126,%127},%128,%129,p,1,1,0,1;}"
    : "+f"(d[0]),"+f"(d[1]),"+f"(d[2]),"+f"(d[3]),"+f"(d[4]),"+f"(d[5]),"+f"(d[6]),"+f"(d[7]),"+f"(d[8]),"+f"(d[9]),"+f"(d[10]),"+f"(d[11]),"+f"(d[12]),"+f"(d[13]),"+f"(d[14]),"+f"(d[15]),"+f"(d[16]),"+f"(d[17]),"+f"(d[18]),"+f"(d[19]),"+f"(d[20]),"+f"(d[21]),"+f"(d[22]),"+f"(d[23]),"+f"(d[24]),"+f"(d[25]),"+f"(d[26]),"+f"(d[27]),"+f"(d[28]),"+f"(d[29]),"+f"(d[30]),"+f"(d[31]),"+f"(d[32]),"+f"(d[33]),"+f"(d[34]),"+f"(d[35]),"+f"(d[36]),"+f"(d[37]),"+f"(d[38]),"+f"(d[39]),"+f"(d[40]),"+f"(d[41]),"+f"(d[42]),"+f"(d[43]),"+f"(d[44]),"+f"(d[45]),"+f"(d[46]),"+f"(d[47]),"+f"(d[48]),"+f"(d[49]),"+f"(d[50]),"+f"(d[51]),"+f"(d[52]),"+f"(d[53]),"+f"(d[54]),"+f"(d[55]),"+f"(d[56]),"+f"(d[57]),"+f"(d[58]),"+f"(d[59]),"+f"(d[60]),"+f"(d[61]),"+f"(d[62]),"+f"(d[63]),"+f"(d[64]),"+f"(d[65]),"+f"(d[66]),"+f"(d[67]),"+f"(d[68]),"+f"(d[69]),"+f"(d[70]),"+f"(d[71]),"+f"(d[72]),"+f"(d[73]),"+f"(d[74]),"+f"(d[75]),"+f"(d[76]),"+f"(d[77]),"+f"(d[78]),"+f"(d[79]),"+f"(d[80]),"+f"(d[81]),"+f"(d[82]),"+f"(d[83]),"+f"(d[84]),"+f"(d[85]),"+f"(d[86]),"+f"(d[87]),"+f"(d[88]),"+f"(d[89]),"+f"(d[90]),"+f"(d[91]),"+f"(d[92]),"+f"(d[93]),"+f"(d[94]),"+f"(d[95]),"+f"(d[96]),"+f"(d[97]),"+f"(d[98]),"+f"(d[99]),"+f"(d[100]),"+f"(d[101]),"+f"(d[102]),"+f"(d[103]),"+f"(d[104]),"+f"(d[105]),"+f"(d[106]),"+f"(d[107]),"+f"(d[108]),"+f"(d[109]),"+f"(d[110]),"+f"(d[111]),"+f"(d[112]),"+f"(d[113]),"+f"(d[114]),"+f"(d[115]),"+f"(d[116]),"+f"(d[117]),"+f"(d[118]),"+f"(d[119]),"+f"(d[120]),"+f"(d[121]),"+f"(d[122]),"+f"(d[123]),"+f"(d[124]),"+f"(d[125]),"+f"(d[126]),"+f"(d[127])
    : "l"(da),"l"(db),"r"(sc));
}
__device__ __forceinline__ void wg_ss128t(float* d, uint64_t da, uint64_t db, int sc) {
  asm volatile("{.reg .pred p; setp.ne.b32 p,%66,0; wgmma.mma_async.sync.aligned.m64n128k16.f32.bf16.bf16 {%0,%1,%2,%3,%4,%5,%6,%7,%8,%9,%10,%11,%12,%13,%14,%15,%16,%17,%18,%19,%20,%21,%22,%23,%24,%25,%26,%27,%28,%29,%30,%31,%32,%33,%34,%35,%36,%37,%38,%39,%40,%41,%42,%43,%44,%45,%46,%47,%48,%49,%50,%51,%52,%53,%54,%55,%56,%57,%58,%59,%60,%61,%62,%63},%64,%65,p,1,1,1,0;}"
    : "+f"(d[0]),"+f"(d[1]),"+f"(d[2]),"+f"(d[3]),"+f"(d[4]),"+f"(d[5]),"+f"(d[6]),"+f"(d[7]),"+f"(d[8]),"+f"(d[9]),"+f"(d[10]),"+f"(d[11]),"+f"(d[12]),"+f"(d[13]),"+f"(d[14]),"+f"(d[15]),"+f"(d[16]),"+f"(d[17]),"+f"(d[18]),"+f"(d[19]),"+f"(d[20]),"+f"(d[21]),"+f"(d[22]),"+f"(d[23]),"+f"(d[24]),"+f"(d[25]),"+f"(d[26]),"+f"(d[27]),"+f"(d[28]),"+f"(d[29]),"+f"(d[30]),"+f"(d[31]),"+f"(d[32]),"+f"(d[33]),"+f"(d[34]),"+f"(d[35]),"+f"(d[36]),"+f"(d[37]),"+f"(d[38]),"+f"(d[39]),"+f"(d[40]),"+f"(d[41]),"+f"(d[42]),"+f"(d[43]),"+f"(d[44]),"+f"(d[45]),"+f"(d[46]),"+f"(d[47]),"+f"(d[48]),"+f"(d[49]),"+f"(d[50]),"+f"(d[51]),"+f"(d[52]),"+f"(d[53]),"+f"(d[54]),"+f"(d[55]),"+f"(d[56]),"+f"(d[57]),"+f"(d[58]),"+f"(d[59]),"+f"(d[60]),"+f"(d[61]),"+f"(d[62]),"+f"(d[63])
    : "l"(da),"l"(db),"r"(sc));
}
__device__ __forceinline__ void wg_ss64(float* d, uint64_t da, uint64_t db, int sc) {
  asm volatile("{.reg .pred p; setp.ne.b32 p,%34,0; wgmma.mma_async.sync.aligned.m64n64k16.f32.bf16.bf16 {%0,%1,%2,%3,%4,%5,%6,%7,%8,%9,%10,%11,%12,%13,%14,%15,%16,%17,%18,%19,%20,%21,%22,%23,%24,%25,%26,%27,%28,%29,%30,%31},%32,%33,p,1,1,0,0;}"
    : "+f"(d[0]),"+f"(d[1]),"+f"(d[2]),"+f"(d[3]),"+f"(d[4]),"+f"(d[5]),"+f"(d[6]),"+f"(d[7]),"+f"(d[8]),"+f"(d[9]),"+f"(d[10]),"+f"(d[11]),"+f"(d[12]),"+f"(d[13]),"+f"(d[14]),"+f"(d[15]),"+f"(d[16]),"+f"(d[17]),"+f"(d[18]),"+f"(d[19]),"+f"(d[20]),"+f"(d[21]),"+f"(d[22]),"+f"(d[23]),"+f"(d[24]),"+f"(d[25]),"+f"(d[26]),"+f"(d[27]),"+f"(d[28]),"+f"(d[29]),"+f"(d[30]),"+f"(d[31])
    : "l"(da),"l"(db),"r"(sc));
}
__device__ __forceinline__ void wg_ss24t(float* d, uint64_t da, uint64_t db, int sc) {
  asm volatile("{.reg .pred p; setp.ne.b32 p,%14,0; wgmma.mma_async.sync.aligned.m64n24k16.f32.bf16.bf16 {%0,%1,%2,%3,%4,%5,%6,%7,%8,%9,%10,%11},%12,%13,p,1,1,1,0;}"
    : "+f"(d[0]),"+f"(d[1]),"+f"(d[2]),"+f"(d[3]),"+f"(d[4]),"+f"(d[5]),"+f"(d[6]),"+f"(d[7]),"+f"(d[8]),"+f"(d[9]),"+f"(d[10]),"+f"(d[11])
    : "l"(da),"l"(db),"r"(sc));
}
__device__ __forceinline__ void wg_ss16t(float* d, uint64_t da, uint64_t db, int sc) {
  asm volatile("{.reg .pred p; setp.ne.b32 p,%10,0; wgmma.mma_async.sync.aligned.m64n16k16.f32.bf16.bf16 {%0,%1,%2,%3,%4,%5,%6,%7},%8,%9,p,1,1,1,0;}"
    : "+f"(d[0]),"+f"(d[1]),"+f"(d[2]),"+f"(d[3]),"+f"(d[4]),"+f"(d[5]),"+f"(d[6]),"+f"(d[7])
    : "l"(da),"l"(db),"r"(sc));
}

template <int N> struct Ring {
  uint32_t slot, ph;
  __device__ __forceinline__ void adv() { if (++slot == N) { slot = 0; ph ^= 1; } }
};

template <int V> struct IC { static constexpr int v = V; };

template <int N, int MID, class F>
__device__ __forceinline__ void gemm1_tile(float* acc, Ring<NS>& r, uint32_t sb, uint32_t bfull, uint32_t bempty, uint32_t bgo, int wg, int w, Scratch* S, F post) {
  uint32_t prevW = 0;
  auto chunk = [&](const int c, auto pc) {
    const uint32_t sx = c & 3;
    if (N == 256 || c >= 4) mbar_wait(bfull + 8 * sx, N == 256 ? (c >> 2) : 0);
    const uint64_t da = mkdesc(sb + sx * SLOT + wg * 8192, 16, 1024, 1);
#pragma unroll
    for (int part = 0; part < 2; part++) {
      const uint32_t sw = NP + r.slot;
      mbar_wait(bfull + 8 * sw, r.ph);
      r.adv();
      if (part == 0) {
        if (N == 256 && c == 0 && wg == 0) bar_sync(7, 384);
        if (N != 256 && c == 0) mbar_wait(bgo + 8, MIDA >= 0);
        if (MID >= 0 && c == MID + 1) mbar_wait(bgo + 8, N != 256);
      }
      wg_fence();
      if (N == 256) {
        const uint64_t db = mkdesc(sb + sw * SLOT, 4096, 1024, 1);
        wg_ss128(acc, da + part * 4, db, (c | part));
        wg_ss128(acc + 64, da + part * 4, db + 512, (c | part));
        wg_ss128(acc, da + part * 4 + 2, db + 128, 1);
        wg_ss128(acc + 64, da + part * 4 + 2, db + 512 + 128, 1);
      } else {
        const uint64_t db = mkdesc(sb + sw * SLOT, 2048, 512, 2);
        wg_ss192(acc, da + part * 4, db, (c | part));
        wg_ss192(acc, da + part * 4 + 2, db + 64, 1);
      }
      wg_commit();
      if (part == 1 && (c == MID || c == 7) && elect()) mbar_arrive(bgo);
      if (pc.v >= 0) post(2 * pc.v + part);
      wg_wait<1>();
      if ((c | part) && elect()) {
        mbar_arrive(bempty + 8 * prevW);
        if (part == 0 && (N != 256 || c <= 4)) mbar_arrive(bempty + 8 * ((c - 1) & 3));
      }
      prevW = sw;
    }
  };
  if (N != 256) { chunk(0, IC<0>()); chunk(1, IC<1>()); }
#pragma unroll 1
  for (int c = N == 256 ? 0 : 2; c < 8; c++) chunk(c, IC<-1>());
  wg_wait<0>();
  if (elect()) { mbar_arrive(bempty + 8 * prevW); if (N != 256) mbar_arrive(bempty + 8 * 3); }
}

template <bool SWAP, int NB>
__device__ __forceinline__ void h_pack(const float* acc, uint32_t* v) {
#pragma unroll
  for (int n = 0; n < 4 * NB; n++) {
    const float* g = acc + (SWAP ? 4 * NB + n : n) * 4;
    const float* u = acc + (SWAP ? n : 4 * NB + n) * 4;
    v[(n >> 2) * 8 + (n & 3)] = hmul2(cvt2relu(g[0], g[1]), cvt2(u[0], u[1]));
    v[(n >> 2) * 8 + 4 + (n & 3)] = hmul2(cvt2relu(g[2], g[3]), cvt2(u[2], u[3]));
  }
}
__device__ __forceinline__ void h_store(const uint32_t* v, bf16* dst) {
  stg128(dst, v[0], v[1], v[2], v[3]);
  stg128(dst + 8 * 1792, v[4], v[5], v[6], v[7]);
}

__host__ __device__ constexpr int hchunk(int i) { return i < 16 ? 7 * (i >> 2) + ((i & 2) ? 5 : 0) + (i & 1) : 7 * ((i - 16) / 3) + 2 + (i - 16) % 3; }

__host__ __device__ constexpr uint64_t htab(int it) { uint64_t t = 0; for (int y = 0; y < N2; y++) t |= (uint64_t)hchunk(N2 * it + y) << (8 * y); return t; }
__host__ __device__ constexpr int hslot(int y) { return y < 4 ? y + 6 : y < 6 ? y : 3; }
__host__ __device__ constexpr int wslot(int y) { return y < 6 ? y * 8192 : CONV_OFF + 34816; }

template <bool SWAP>
__global__ void __launch_bounds__(512, 1) fused_kernel(const __grid_constant__ Params p) {
  extern __shared__ uint8_t smem_raw[];
  Scratch* const S = (Scratch*)__cvta_global_to_generic(p.sc & ~1ull);
  int w;
  {
    uint32_t smid;
    asm volatile("mov.u32 %0, %%smid;" : "=r"(smid));
    if (p.sc & 1) {
      if (smid < 64) w = ((smid >> 1) & 7) * 16 + (smid >> 4) * 2 + (smid & 1);
      else if (smid < 120) { const int t = smid - 64; w = (1 + (t >> 1) % 7) * 16 + 8 + (t / 14) * 2 + (t & 1); }
      else if (smid < 124) w = 128 + smid - 120;
      else w = 8 + smid - 124;
    } else w = blockIdx.x;
    if (w >= 128) {
      if (threadIdx.x < 32) {
        uint32_t ep = 0;
        if (threadIdx.x == 0) { ep = S->epoch[w] + 1; S->epoch[w] = ep; }
        ep = __shfl_sync(0xffffffffu, ep, 0);
#pragma unroll 1
        for (int i = 0; i < 4; i++) { __nanosleep(500); poll_flags(S->epoch + i * 32 + threadIdx.x, true, ep); }
      }
      return;
    }
  }
  w = ((w >> 5) * 4 + ((w >> 2) & 3)) * 8 + ((w >> 4) & 1) * 4 + (w & 3);
  const int G = w >> 3, m = w & 7;
  const uint32_t sb = (s2u(smem_raw) + 1023) & ~1023u;
  const uint32_t bfull = sb + BAR_OFF, bempty = bfull + 8 * NSLOT, bep = bempty + 8 * NSLOT, bardy = bep + 8, bflag = bardy + 8, bxt = bflag + 8, bus = bxt + 8, bgo = bus + 8, sep = bgo + 16, bf2 = sep + 8, be2 = bf2 + 8 * N2;
  const uint32_t cv = sb + CONV_OFF;
  const int tid = threadIdx.x, warp = __shfl_sync(0xffffffffu, tid >> 5, 0), lane = tid & 31;
  uint32_t vla = 0, vai = 0, vcr = 0, vci = 0, vdt = 0;
  if (warp >= 8) {
    const int d = 4 * w + (warp & 3), o = d * 128 + (warp & 4) * 16 + lane * 2;
    vla = ldg_nc32(p.logA + o); vai = ldg_nc32(p.Aim + o); vcr = ldg_nc32(p.Cre + o); vci = ldg_nc32(p.Cim + o);
    vdt = ldg_nc16(p.logdt + d);
  }
  if (tid == 0) {
    TR(0);
    TG(63);
    for (int i = 0; i < NSLOT; i++) { mbar_init(bfull + 8 * i, 1); mbar_init(bempty + 8 * i, 8); }
    mbar_init(bep, 1); mbar_init(bardy, 1); mbar_init(bflag, 1); mbar_init(bxt, 1); mbar_init(bus, 1); mbar_init(bgo, 12); mbar_init(bgo + 8, 4);

    asm volatile("fence.mbarrier_init.release.cluster;" ::: "memory");
    prefetch_map(&p.x); prefetch_map(&p.wA);
  }
  if (tid == 32) {
    for (int i = 0; i < N2; i++) { mbar_init(bf2 + 8 * i, 1); mbar_init(be2 + 8 * i, 4); }
    asm volatile("fence.mbarrier_init.release.cluster;" ::: "memory");
  }
  KT(41);
  __syncthreads();
  KT(42);
  const int p2 = m >> 1, odd = m & 1;
  const int atomA = 7 * p2 + (odd ? 5 : 0), blkB = 14 * p2 + (odd ? 7 : 4);

  if (warp < 4) {
    asm volatile("setmaxnreg.dec.sync.aligned.u32 40;");
    if (warp < 1) {
      Ring<NS> r{0, 1};
#pragma unroll 1
      for (int s = 0; s < 32; s++) {
        const uint32_t dst = sb + (NP + r.slot) * SLOT, bar = bfull + 8 * (NP + r.slot);
        if (s == NS - 2) bar_sync(9, 160);
        mbar_wait(bempty + 8 * (NP + r.slot), r.ph);
        if (elect()) {
          if (s < 16) {
            mbar_expect(bar, 16384);
            tma4d(dst, &p.wA, 0, s * 32, atomA, 0, bar);
          } else {
            const int k = ((s + 8) & 15) * 32;
            mbar_expect(bar, 12288);
            tma4d(dst, &p.wB, 0, k, blkB, 0, bar);
          }
          if (s == 5) { prefetch_map(&p.wB); prefetch_map(&p.h); }
        }
        r.adv();
      }
      mbar_wait(bflag, 0);
      if (lane == 0) TR(8);
#pragma unroll 1
      for (int it = 0; it < 4; it++) {
        const uint64_t tab = it < 1 ? htab(0) : it < 2 ? htab(1) : it < 3 ? htab(2) : htab(3);
#pragma unroll
        for (int y = 0; y < N2; y++) {
          const int c = (int)(tab >> (8 * y)) & 31;
          if (y == 2 && it == 2) { mbar_wait(bflag, 1); if (lane == 0) TR(9); }
          mbar_wait(it ? be2 + 8 * y : bempty + 8 * hslot(y), it ? ~it & 1 : (y >> 1) == 2);
          if (elect()) tma2d(sb + hslot(y) * SLOT, &p.h, c * 64, G * 128, bf2 + 8 * y);
        }
      }
    } else if (warp > 2) {
#pragma unroll 1
      for (int n = 0; n < 12; n++) {
        const uint32_t dst = sb + (n & 3) * SLOT, bar = bfull + 8 * (n & 3);
        mbar_wait(bempty + 8 * (n & 3), ((n >> 2) & 1) ^ 1);
        if (elect()) {
          mbar_expect(bar, 16384);
          tma4d(dst, &p.x, (n & 7) * 64, 0, G * 4, 0, bar);
          if (n == XTN) {
            mbar_expect(bxt, 16384);
            tma4d(cv, &p.x, m * 64, 0, G * 4, 0, bxt);
          }
          if (n == 3) { prefetch_map(&p.us); prefetch_map(&p.wd); prefetch_map(&p.out); }
          if (n == 6) asm volatile("cp.async.bulk.prefetch.L2.global [%0], %1;" ::"l"(p.Wd + (size_t)w * 14 * 512), "r"(14336) : "memory");
        }
      }
#pragma unroll 1
      for (int it = 0; it < 4; it++) {
        const uint64_t tab = it < 1 ? htab(0) : it < 2 ? htab(1) : it < 3 ? htab(2) : htab(3);
#pragma unroll
        for (int y = 0; y < N2; y++) {
          const int c = (int)(tab >> (8 * y)) & 31;
          mbar_wait(it ? be2 + 8 * y : y < 6 ? bempty + 8 * (y >> 1) : bgo, it ? ~it & 1 : 0);
          if (elect()) {
            mbar_expect(bf2 + 8 * y, 24576);
            tma5d(sb + wslot(y), &p.wd, m * 64, 0, 0, 0, 2 * c, bf2 + 8 * y);
          }
        }
      }
    } else if (warp < 2) {
      const uint4 w0 = ldg_nc(p.gw + lane * 8), w1 = ldg_nc(p.gw + 256 + lane * 8);
      const int row0 = G * 128 + m * 16;
      float mine = 0.f, p1 = 0.f, p2 = 0.f;
      auto mrg = [&](float a, float b, int o) { const bool hi = lane & o; return (hi ? b : a) + __shfl_xor_sync(0xffffffffu, hi ? a : b, o); };
#pragma unroll 1
      for (int i = 0; i < 16; i += 2) {
        const bf16* xr = p.u + (size_t)(row0 + i) * 512 + lane * 8;
        const uint4 a0 = ldg_nc(xr), a1 = ldg_nc(xr + 256), b0 = ldg_nc(xr + 512), b1 = ldg_nc(xr + 768);
        uint32_t t;
        float sa, sc;
        t = hmul2(a0.x, w0.x); sa = blo(t) + bhi(t);
        t = hmul2(a0.y, w0.y); sa += blo(t) + bhi(t);
        t = hmul2(a0.z, w0.z); sa += blo(t) + bhi(t);
        t = hmul2(a0.w, w0.w); sa += blo(t) + bhi(t);
        t = hmul2(a1.x, w1.x); sa += blo(t) + bhi(t);
        t = hmul2(a1.y, w1.y); sa += blo(t) + bhi(t);
        t = hmul2(a1.z, w1.z); sa += blo(t) + bhi(t);
        t = hmul2(a1.w, w1.w); sa += blo(t) + bhi(t);
        t = hmul2(b0.x, w0.x); sc = blo(t) + bhi(t);
        t = hmul2(b0.y, w0.y); sc += blo(t) + bhi(t);
        t = hmul2(b0.z, w0.z); sc += blo(t) + bhi(t);
        t = hmul2(b0.w, w0.w); sc += blo(t) + bhi(t);
        t = hmul2(b1.x, w1.x); sc += blo(t) + bhi(t);
        t = hmul2(b1.y, w1.y); sc += blo(t) + bhi(t);
        t = hmul2(b1.z, w1.z); sc += blo(t) + bhi(t);
        t = hmul2(b1.w, w1.w); sc += blo(t) + bhi(t);
        float v = mrg(sa, sc, 1);
        if (i & 2) {
          v = mrg(p1, v, 2);
          if (i & 4) {
            v = mrg(p2, v, 4);
            if (i & 8) mine = mrg(mine, v, 8); else mine = v;
          } else p2 = v;
        } else p1 = v;
      }
      mine += __shfl_xor_sync(0xffffffffu, mine, 16);
      if (lane < 16) {
        const float s = __bfloat162float(__float2bfloat16(mine));
        const float gv = 1.f / (1.f + __expf(-s));
        const int t = row0 + lane;
        S->g[t] = __float2bfloat16(gv);
      }
      mbar_wait(bep, 0);
      uint32_t ep;
      asm volatile("ld.shared.u32 %0, [%1];" : "=r"(ep) : "r"(sep) : "memory");
      bar_sync(1, 288);
      if (lane == 0) TR(13);
      publish(S->flag + (G * 8 + (lane & 7)) * 32 + m, ep, lane < 8);
      if (lane == 0) TR(10);
      bar_arrive(5, 64);
      bar_sync(2, 288);
      publish(S->flag + (G * 8 + (lane & 7)) * 32 + 8 + m, ep, lane < 8);
      if (lane == 0) TR(11);
      bar_arrive(5, 64);
    } else {
      uint32_t ep = 0;
      if (lane == 0) {
        ep = S->epoch[w] + 1;
        S->epoch[w] = ep;
        asm volatile("st.shared.u32 [%0], %1;" ::"r"(sep), "r"(ep) : "memory");
        mbar_arrive(bep);
        prefetch_map(&p.ut);
      }
      ep = __shfl_sync(0xffffffffu, ep, 0);
      bar_sync(6, 160);
      if (lane < 4) {
        asm volatile("cp.async.bulk.tensor.3d.global.shared::cta.bulk_group [%0, {%2, %3, %4}], [%1];" ::"l"(&p.ut), "r"(cv + lane * 4096), "r"(G * 32), "r"(3 - lane), "r"(m * 64) : "memory");
        asm volatile("cp.async.bulk.commit_group;" ::: "memory");
        asm volatile("cp.async.bulk.wait_group.read 0;" ::: "memory");
      }
      __syncwarp();
      bar_arrive(10, 160);
      asm volatile("cp.async.bulk.wait_group 0;" ::: "memory");
      __syncwarp();
      publish(S->fu + (m * 16 + (lane & 15)) * 32 + G, ep, lane < 16);
      if (lane == 0) TR(19);
      if (PSU) __nanosleep(PSU);
      poll_flags(S->fu + w * 32 + lane, lane < 16, ep);
      if (lane == 0) TR(28);
      bar_sync(11, 160);
      if (elect()) {
        mbar_expect(bus, 16 * UST);
#pragma unroll
        for (int c = 0; c < 4; c++) tma2d(cv + CHB + c * CHS, &p.us, -16, w * 16 + c * 4, bus);
      }
      bar_sync(5, 64);
      if (PSA) __nanosleep(PSA);
      poll_flags(S->flag + w * 32 + lane, lane < 8, ep);
      if (lane == 0) TR(15);
      if (elect()) mbar_arrive(bflag);
      bar_sync(5, 64);
      if (PSB) __nanosleep(PSB);
      poll_flags(S->flag + w * 32 + 8 + lane, lane < 8, ep);
      if (lane == 0) TR(16);
      if (elect()) mbar_arrive(bflag);
      bar_sync(0, 160);
      if (PS0) __nanosleep(PS0);
      poll_flags(S->flag + w * 32 + 16 + lane, lane < 16, ep);
      if (elect()) mbar_arrive(bardy);
      if (lane == 0) TR(12);
    }
    return;
  }
  float ka[2][3][4];
  if (warp >= 8) {
    constexpr int KS = 272;
    const int wq = warp & 3, r8 = lane & 7, mi = lane >> 3;
    const uint32_t stg = (warp >= 12 ? cv + WE4 : sb + (NSLOT - 2) * SLOT) + wq * 30 * KS;
    const uint32_t ss = stg + (mi >> 1) * KS + (mi & 1) * 128 + r8 * 16;
    const uint32_t lx = stg + ((mi & 1) ? 29 : 21 + r8) * KS + (mi >> 1) * 128;
    const uint32_t l01 = stg + ((mi >> 1) ? 8 + ((0x44322210u >> (4 * r8)) & 7) : r8) * KS + (mi & 1) * 128;
    const uint32_t l2 = stg + (13 + r8) * KS + (mi & 1) * 128 + (mi >> 1) * 16;
    float kb[2][3][4];
#pragma unroll
    for (int i = 0; i < 24; i++) (&kb[0][0][0])[i] = 0.f;
    const float dt = bfr(expf(blo(vdt)));
    uint32_t mx = __vmaxu2(vcr & 0x7fff7fffu, vci & 0x7fff7fffu);
    mx = __reduce_max_sync(0xffffffffu, max(mx & 0xffffu, mx >> 16));
    const uint32_t ex = min(max(mx >> 7, 9u), 254u);
    const float sc = __uint_as_float((262u - ex) << 23), fin = __uint_as_float((ex - 8u) << 23) * (2.f * dt);
    if (tid == 384) TR(7);
    {
      const uint32_t ea = cvt2(__expf(blo(vla)), __expf(bhi(vla)));
      const float aa = -blo(ea) * dt * 1.4426950408889634f, ab = -bhi(ea) * dt * 1.4426950408889634f, ba = blo(vai) * dt, bb = bhi(vai) * dt;
      float2 wa = cexp2(aa, ba), wb = cexp2(ab, bb), va = cexp2(64.f * aa, 64.f * ba), vb = cexp2(64.f * ab, 64.f * bb);
      const HC P0 = {cvth2(blo(vcr) * sc, bhi(vcr) * sc), cvth2(-blo(vci) * sc, -bhi(vci) * sc)};
      const HC h1 = cvthc(wa, wb), h64 = cvthc(va, vb);
      wa = csq(wa); wb = csq(wb); va = csq(va); vb = csq(vb);
      const HC h2 = cvthc(wa, wb);
      wa = csq(wa); wb = csq(wb); va = csq(va); vb = csq(vb);
      const HC h4 = cvthc(wa, wb), h256 = cvthc(va, vb);
      const HC P2 = hmulc(P0, h2), P4 = hmulc(P0, h4), P6 = hmulc(P4, h2);
      KT(32);
      stsmc(ss + 6 * KS, hmulc(P0, h1), P0);
      stsmc(ss + 4 * KS, hmulc(P2, h1), P2);
      stsmc(ss + 2 * KS, hmulc(P4, h1), P4);
      stsmc(ss, hmulc(P6, h1), P6);
      wa = csq(wa); wb = csq(wb); va = csq(va); vb = csq(vb);
      const HC h8 = cvthc(wa, wb), h512 = cvthc(va, vb);
      const HC P8 = hmulc(P0, h8), Q8 = hmulc(P8, h256), Q4 = hmulc(P4, h256), R8 = hmulc(P8, h512), S8 = hmulc(Q8, h512);
      stsmc(ss + 8 * KS, Q8, hmulc(P6, h256));
      stsmc(ss + 10 * KS, Q4, hmulc(P2, h256));
      stsmc(ss + 12 * KS, hmulc(P0, h256), R8);
      stsmc(ss + 14 * KS, S8, hmulc(P4, h512));
      wa = csq(wa); wb = csq(wb); va = csq(va); vb = csq(vb);
      const HC h16 = cvthc(wa, wb), h1024 = cvthc(va, vb), h32 = cvthc(csq(wa), csq(wb)), h24 = hmul(h8, h16);
      stsmc(ss + 16 * KS, hmulc(Q4, h512), hmulc(P8, h1024));
      stsmc(ss + 18 * KS, hmulc(Q8, h1024), hmulc(R8, h1024));
      stsmc(ss + 20 * KS, hmulc(S8, h1024), HC{0x3c003c00u, 0u});
      stsmc(ss + 22 * KS, h8, h16);
      stsmc(ss + 24 * KS, h24, h32);
      stsmc(ss + 26 * KS, hmul(h8, h32), hmul(h16, h32));
      stsmc(ss + 28 * KS, hmul(h24, h32), h64);
      __syncwarp();
      KT(33);
    }
#pragma unroll KUNR
    for (int k2 = 0; k2 < 8; k2 += 2) {
      uint32_t b2[4];
      ldsm4(b2, l2 + k2 * 16);
#pragma unroll
      for (int k1 = 0; k1 < 2; k1++) {
        uint32_t xw[4], b[4];
        ldsm4(xw, lx + (k2 + k1) * 16);
        ldsm4(b, l01 + (k2 + k1) * 16);
        const HC ww = {xw[1], xw[3]}, x1 = hmul(HC{xw[0], xw[2]}, ww), x2 = hmul(x1, ww), x3 = hmul(x2, ww);
        mma_f16(kb[1][0], x1.re, x2.re, x1.im, x2.im, b[0], b[1]);
        mma_f16(kb[1][1], x1.re, x2.re, x1.im, x2.im, b[2], b[3]);
        mma_f16(kb[1][2], x1.re, x2.re, x1.im, x2.im, b2[2 * k1], b2[2 * k1 + 1]);
        mma_f16(kb[0][0], xw[0], x3.re, xw[2], x3.im, b[0], b[1]);
        mma_f16(kb[0][1], xw[0], x3.re, xw[2], x3.im, b[2], b[3]);
        mma_f16(kb[0][2], xw[0], x3.re, xw[2], x3.im, b2[2 * k1], b2[2 * k1 + 1]);
      }
      KT(34 + k2 / 2);
    }
#pragma unroll
    for (int n = 0; n < 3; n++)
#pragma unroll
      for (int e = 0; e < 2; e++) {
        ka[0][n][e] = kb[0][n][e] * fin; ka[0][n][2 + e] = kb[1][n][e] * fin;
        ka[1][n][e] = kb[1][n][2 + e] * fin; ka[1][n][2 + e] = kb[0][n][2 + e] * fin;
      }
    asm volatile("" ::"f"(ka[1][2][3]), "f"(ka[1][1][3]), "f"(ka[1][0][3]) : "memory");
    bar_arrive(7, 384);
    KT(40);
    const uint32_t pa = sb + (NSLOT - 2) * SLOT + wq * 30 * KS + lane * 16;
    if (warp < 12) {
#pragma unroll
      for (int i = 0; i < 6; i++) { const float* v = &ka[0][0][0] + 4 * i; sts128(pa + i * 512, __float_as_uint(v[0]), __float_as_uint(v[1]), __float_as_uint(v[2]), __float_as_uint(v[3])); }
      fence_async_smem();
    }
    bar_sync(8, 256);
    if (tid == 384) TR(17);
    if (warp >= 12) {
#pragma unroll
      for (int i = 0; i < 6; i++) {
        uint32_t v[4];
        lds128(v, pa + i * 512);
#pragma unroll
        for (int k = 0; k < 4; k++) (&ka[0][0][0])[4 * i + k] += __uint_as_float(v[k]);
      }
      fence_async_smem();
      bar_arrive(9, 160);
      bar_arrive(11, 160);
    }
  }
  if (warp < 12) {
    asm volatile("setmaxnreg.inc.sync.aligned.u32 160;");
    const int wg = (warp >> 2) - 1, wq = warp & 3, g = lane >> 2, q = lane & 3;
    if (wg == 0) {
      mbar_wait(bxt, 0);
      if (tid == 128) TR(14);
      uint32_t v[8][4];
#pragma unroll
      for (int db = 0; db < 8; db++) ldsm4t(v[db], cv + (wq * 32 + lane) * 128 + ((db ^ (lane & 7)) << 4));
      __syncwarp();
#pragma unroll
      for (int db = 0; db < 8; db++) sts128(cv + wq * 4096 + db * 512 + lane * 16, v[db][0], v[db][1], v[db][2], v[db][3]);
      fence_async_smem();
      bar_arrive(6, 160);
      if (tid == 128) TR(18);
    }
    float acc[128];
    Ring<NS> r{0, 0};
    bf16* hrow = S->h + (size_t)(G * 128 + wg * 64 + wq * 16 + g) * 1792 + q * 8;
    gemm1_tile<256, MIDA>(acc, r, sb, bfull, bempty, bgo, wg, w, S, [](int) {});
    if (tid == 128) { TR(1); TG(59); }
    uint32_t hv[32];
    h_pack<SWAP, 4>(acc, hv);
    float accB[96];
    gemm1_tile<192, MIDB>(accB, r, sb, bfull, bempty, bgo, wg, w, S, [&](int i) {
      h_store(hv + 8 * i, hrow + atomA * 64 + i * 32);
      if (i == 3) { bar_arrive(1, 288); if (tid == 128) TR(2); }
    });
    if (tid == 128) { TR(3); TG(60); }
    h_pack<SWAP, 3>(accB, hv);
    auto storeB = [&]() {
#pragma unroll
      for (int i = 0; i < 3; i++) h_store(hv + 8 * i, hrow + (blkB + i) * 32);
      bar_arrive(2, 288);
      if (tid == 128) TR(4);
    };
    if (ESY < 0 || wg == 1) storeB();
    if (wg == 0) {
      float acc2[64];
      uint4 av[8], gv[4];
      auto round = [&](const int it, auto last) {
        uint32_t sv;
        asm volatile("shfl.sync.idx.b32 %0, %1, 0, 31, -1;" : "=r"(sv) : "r"(sb));
        const uint64_t d0 = mkdesc(sv, 16, 1024, 1);
#pragma unroll
        for (int y = 0; y < N2; y++) {
          if (last.v && y == ALD - 21) {
            mbar_wait(bardy, 0);
            const bf16* ap = S->aT + (size_t)(m * 64 + wq * 16 + g) * 2048 + G * 32 + q * 8;
#pragma unroll
            for (int a = 0; a < 4; a++) {
              av[2 * a] = ldg_cg(ap + a * 512);
              av[2 * a + 1] = ldg_cg(ap + 8 * 2048 + a * 512);
              gv[a] = ldg_cg(S->g + G * 128 + q * 32 + a * 8);
            }
          }
          mbar_wait(bf2 + 8 * y, it & 1);
          if (tid == 128 && !((y + it) & 1)) TR(32 + (7 * it + y) / 2);
          if (!last.v && y == (MID2 + 1) % N2 && it == (MID2 + 1) / N2) mbar_wait(bgo + 8, 1);
          wg_fence();
#pragma unroll
          for (int kk = 0; kk < 4; kk++) wg_ss128t(acc2, d0 + wslot(y) / 16 + kk * 128, d0 + hslot(y) * (SLOT / 16) + kk * 2, (last.v | y | kk) ? 1 : it);
          wg_commit();
          if (!last.v && y == MID2 % N2 && it == MID2 / N2 && elect()) mbar_arrive_n(bgo, 2);
          if (!last.v && y == ESY && it == 0) storeB();
          if (!last.v || y == 0) {
            wg_wait<1>();
            if ((y || it) && elect()) mbar_arrive(be2 + 8 * ((y + N2 - 1) % N2));
          }
        }
      };
      mbar_wait(bgo + 8, 0);
#pragma unroll 1
      for (int it = 0; it < 3; it++) round(it, IC<0>());
      round(3, IC<1>());
      wg_wait<0>();
      if (tid == 128) { TR(5); TG(61); }
      const int mi = lane >> 3, rr = lane & 7;
      const uint32_t st0 = cv + 16384 + (rr + (mi >> 1) * 8) * 128 + (((wq * 2 + (mi & 1)) ^ rr) << 4);
#pragma unroll
      for (int a = 0; a < 4; a++) {
        const uint32_t gg[4] = {gv[a].x, gv[a].y, gv[a].z, gv[a].w};
        const uint32_t a0[4] = {av[2 * a].x, av[2 * a].y, av[2 * a].z, av[2 * a].w};
        const uint32_t a1[4] = {av[2 * a + 1].x, av[2 * a + 1].y, av[2 * a + 1].z, av[2 * a + 1].w};
        uint32_t o0[4], o1[4];
#pragma unroll
        for (int n = 0; n < 4; n++) {
          const float* d = acc2 + (4 * a + n) * 4;
          const uint32_t og = hsub2(0x3f803f80u, gg[n]);
          o0[n] = hadd2(hmul2(gg[n], a0[n]), hmul2(og, cvt2(d[0], d[1])));
          o1[n] = hadd2(hmul2(gg[n], a1[n]), hmul2(og, cvt2(d[2], d[3])));
        }
        stsm4t(st0 + (4 * a) * 1024, o0[0], o1[0], o0[1], o1[1]);
        stsm4t(st0 + (4 * a + 2) * 1024, o0[2], o1[2], o0[3], o1[3]);
        if ((a + 1) % (4 / NOUT) == 0) {
          asm volatile("fence.proxy.async.shared::cta;" ::: "memory");
          bar_arrive(12 + a / (4 / NOUT), 160);
        }
      }
    } else if (wq == 0) {
#pragma unroll
      for (int a = 0; a < NOUT; a++) {
        bar_sync(12 + a, 160);
        if (lane == 0) tma_store4d(&p.out, cv + 16384 + a * (16384 / NOUT), m * 64, 0, G * 4, a * (16 / NOUT));
      }
      if (lane == 0) {
        TR(26);
        asm volatile("cp.async.bulk.commit_group;" ::: "memory");
        asm volatile("cp.async.bulk.wait_group.read 0;" ::: "memory");
        TR(6);
        TG(62);
      }
    }
  } else {
    asm volatile("setmaxnreg.inc.sync.aligned.u32 152;");
    const int ct = tid - 384, wq = warp & 3, g = lane >> 2, q = lane & 3;
    {
      const uint32_t kl = cv + CHB + wq * CHS + KLO;
      const uint32_t vsk = ldg_nc16(p.Dsk + 4 * w + wq);
#pragma unroll
      for (int i = 0; i < 4; i++) if (i < 3 || lane < 11) sts128(kl + (i * 32 + lane) * 16, 0, 0, 0, 0);
      __syncwarp();
      const float dsk = blo(vsk);
      if (lane == 3) ka[0][0][1] += dsk;
      if (lane == 28) {
        const uint32_t k2 = cvt2(ka[1][1][2], ka[1][2][3]);
        ka[1][1][2] = 0.f;
        ka[1][1][3] -= blo(k2);
        sts16(kl + 695 * 2, k2);
        sts16(kl + 703 * 2, k2 >> 16);
      }
      stsm4(kl + (32 - lane) * 16, cvt2(ka[0][0][0], ka[0][0][1]), cvt2(ka[0][0][2], ka[0][0][3]), cvt2(ka[1][0][0], ka[1][0][1]), cvt2(ka[1][0][2], ka[1][0][3]));
      stsm4(kl + (68 - lane) * 16, cvt2(ka[0][1][0], ka[0][1][1]), cvt2(ka[0][1][2], ka[0][1][3]), cvt2(ka[1][1][0], ka[1][1][1]), cvt2(ka[1][1][2], ka[1][1][3]));
      const uint32_t sa = kl + 2 * (q < 2 ? (q ? 623 : 694) - g : 839 - 32 * q - (g >> 1) + 72 * (g & 1)), sr = q < 2 ? 16 : 8;
#pragma unroll
      for (int r = 0; r < 4; r++) {
        const uint32_t k2 = cvt2(ka[r >> 1][2][(r & 1) * 2], ka[r >> 1][2][(r & 1) * 2 + 1]);
        sts16(sa - r * sr, k2);
        sts16(sa - (r + 4) * sr, k2 >> 16);
      }
      bar_sync(10, 160);
      if (ct < 125) sts128(cv + WE4 - 16 + (ct >= 63 ? WO4 - WE4 - 992 : 0) + ct * 16, 0, 0, 0, 0);
      if (ct < 96) { const uint32_t a = cv + WE8 + (ct >= 48 ? 1792 - 768 : 0) + ct * 16; sts128(a, 0, 0, 0, 0); if (ct < 95) sts128(a + (WO8 - WE8), 0, 0, 0, 0); }
    }
    int tpos, tblk;
    bool tzero = false;
    if (ct < 66) { tpos = (ct >> 1) + 36 * (ct & 1); tblk = 70 - (ct & ~1) + (ct & 1); }
    else if (ct < 103) { tpos = ct + 3; tblk = (tpos >= 87 ? 183 : tpos >= 78 ? 185 : 187) - tpos; tzero = tpos == 88 || tpos == 97; }
    else { const int k = ct - 103; tblk = k + (k < 6 ? 0 : k < 12 ? 66 : k < 14 ? 85 : 94); tpos = 33; tzero = true; }
    if (tzero) tpos = 33;
    const int np = ct < 96 ? ct : -1;
    auto a8 = [](int R) { return 16 * (R & 7) + 256 * (R >> 4) + 1792 * ((R >> 3) & 1); };
#pragma unroll 1
    for (int c = 0; c < 4; c++) {
      const uint32_t chb = cv + CHB + c * CHS;
      if (ct < 119 && (c == 0 || !tzero)) {
        uint32_t z[8], y[7];
        lds128(z, chb + KLO + tpos * 16);
        lds128(z + 4, chb + KLO + tpos * 16 + 16);
#pragma unroll
        for (int k = 0; k < 7; k++) y[k] = __byte_perm(z[k], z[k + 1], 0x5432);
        const uint32_t ta = cv + tblk * TS;
#pragma unroll
        for (int k = 0; k < 4; k++) {
          sts128(ta + 32 * k, y[3 - k], y[4 - k], y[5 - k], y[6 - k]);
          sts128(ta + 32 * k + 16, z[3 - k], z[4 - k], z[5 - k], z[6 - k]);
        }
      }
      if (c == 0) { mbar_wait(bus, 0); if (ct == 0) TR(29); }
      if (ct < 97) {
        uint32_t v[16];
#pragma unroll
        for (int k = 0; k < 4; k++) { const int J = 2 * np - 1 + k; lds128(v + 4 * k, chb + (3 - (J & 3)) * UST + 16 * ((J >> 2) + 8)); }
        float u[32], s2[32], t3[32], e4[32];
#pragma unroll
        for (int k = 3; k < 28; k++) u[k] = (k & 1) ? bhi(v[k >> 1]) : blo(v[k >> 1]);
#pragma unroll
        for (int k = 4; k < 27; k++) s2[k] = u[k] + u[k + 1];
#pragma unroll
        for (int k = 4; k < 23; k++) t3[k] = u[k - 1] + s2[k];
#pragma unroll
        for (int k = 6; k < 24; k++) e4[k] = t3[k - 1] + s2[k + 1];
        const bool sw = lane & 4;
        const uint32_t a4 = cv + WE4 + 1024 + 32 * np + (sw ? 16 : 0);
        uint32_t o[8];
#pragma unroll
        for (int k = 0; k < 8; k++) o[k] = cvt2(e4[8 + 2 * k], e4[9 + 2 * k]);
        sts128(a4, sw ? o[4] : o[0], sw ? o[5] : o[1], sw ? o[6] : o[2], sw ? o[7] : o[3]);
        sts128(a4 ^ 16, sw ? o[0] : o[4], sw ? o[1] : o[5], sw ? o[2] : o[6], sw ? o[3] : o[7]);
#pragma unroll
        for (int k = 0; k < 8; k++) o[k] = cvt2(t3[4 + 2 * k], t3[5 + 2 * k]);
        sts128(a4 + 4096, sw ? o[4] : o[0], sw ? o[5] : o[1], sw ? o[6] : o[2], sw ? o[7] : o[3]);
        sts128((a4 ^ 16) + 4096, sw ? o[0] : o[4], sw ? o[1] : o[5], sw ? o[2] : o[6], sw ? o[3] : o[7]);
        if (np < 64) {
          float o8[32];
#pragma unroll
          for (int k = 7; k < 24; k++) o8[k] = e4[k - 1] + s2[k + 2];
          const uint32_t ae = cv + WE8 + a8(np + 49);
#pragma unroll
          for (int k = 0; k < 8; k++) o[k] = cvt2(o8[8 + 2 * k], o8[9 + 2 * k]);
          sts128(cv + WO8 + 128 + a8(np + 48), o[0], o[1], o[2], o[3]);
          if (np < 63) sts128(ae + (WO8 - WE8), o[4], o[5], o[6], o[7]);
#pragma unroll
          for (int k = 0; k < 8; k++) o[k] = cvt2(o8[7 + 2 * k] + s2[11 + 2 * k], o8[8 + 2 * k] + s2[12 + 2 * k]);
          if (np < 63) { sts128(ae, o[0], o[1], o[2], o[3]); sts128(ae + 128, o[4], o[5], o[6], o[7]); }
#pragma unroll
          for (int k = 0; k < 8; k++) o[k] = cvt2(s2[4 + 2 * k], s2[5 + 2 * k]);
          const uint32_t as = cv + WSS + 16 * (np & 7) + 256 * (np >> 4) + ((np & 8) ? 0 : 1024);
          if (np >= 0) { sts128(as, o[0], o[1], o[2], o[3]); sts128(as + 128, o[4], o[5], o[6], o[7]); }
        }
      }
      float fix = 0.f;
      if (ct == 123 || ct == 127) {
        const uint32_t u01 = lds32(chb + 3 * UST + 128);
        fix = bhi(lds32(chb + KLO + 694 * 2)) * (ct == 127 ? blo(u01) + bhi(u01) : blo(u01));
      }
      fence_async_smem();
      __syncwarp();
      if (lane == 0) {
        asm volatile("cp.async.bulk.wait_group.read 0;" ::: "memory");
        mbar_arrive(bgo);
      }
      if (ct == 0) TR(46 + 3 * c);
      mbar_wait(bgo, c & 1);
      if (ct == 0) TR(47 + 3 * c);
      float dD[32], d4[12], d8[8];
      wg_fence();
      {
        const uint64_t da = mkdesc(cv + WE8, WO8 - WE8, 128, 0), db = mkdesc(cv + 77 * TS, 9 * TS, TS, 0);
#pragma unroll
        for (int s = 0; s < 8; s++) wg_ss16t(d8, da + 16 * (s >> 1) + 112 * (s & 1), db + (7 - s) * (TS / 16), s);
        wg_ss16t(d8, mkdesc(cv + WSS, 1024, 128, 0), mkdesc(cv + 95 * TS, TS, TS, 0), 1);
      }
      {
        const uint64_t da = mkdesc(cv + WE4, WO4 - WE4, 384, 0), db = mkdesc(cv + 97 * TS, 11 * TS, TS, 0);
#pragma unroll
        for (int s = 0; s < 11; s++) wg_ss24t(d4, da + 8 * s, db + (10 - s) * (TS / 16), s);
      }
      {
        const uint64_t da = mkdesc(cv, 2 * TS, TS, 0), db = mkdesc(chb, UST, 128, 0);
#pragma unroll
        for (int s = 0; s < 18; s++) wg_ss64(dD, da + (68 - 4 * s) * (TS / 16), db + ((s & 1) ? 0 : 2 * UST / 16) + (s >> 1), s);
      }
      wg_commit();
      if (lane == 0) mbar_arrive(bgo + 8);
      wg_wait<0>();
      if (ct == 0) TR(48 + 3 * c);
      bar_sync(3, 128);
      {
        const int J = 64 + 48 * wq + lane, J8 = 32 * wq + 2 * ((lane >> 4) * 8 + (lane & 7)) + ((lane >> 3) & 1);
        const uint32_t y4 = chb + (J & 3) * 1056 + (J >> 2) * 16;
        stsm4t(y4, cvt2(d4[0], d4[1]), cvt2(d4[4], d4[5]), cvt2(d4[8], d4[9]), cvt2(d4[2], d4[3]));
        stsm2t(y4 + 128, cvt2(d4[6], d4[7]), cvt2(d4[10], d4[11]));
        stsm4t(chb + 4224 + (J8 & 3) * 544 + (J8 >> 2) * 16, cvt2(d8[0], d8[1]), cvt2(d8[2], d8[3]), cvt2(d8[4], d8[5]), cvt2(d8[6], d8[7]));
      }
      bar_sync(3, 128);
      {
        const uint32_t ya = chb + wq * 1056 + lane * 16;
        uint32_t l4[6], l8[4], o[8];
        ldsm4t(l4, ya + 256);
        ldsm2t(l4 + 4, ya + 768);
        ldsm4t(l8, chb + 4224 + wq * 544 + lane * 16);
        dD[5] += fix;
#pragma unroll
        for (int nt = 0; nt < 8; nt++) {
          float v0 = dD[4 * nt], v1 = dD[4 * nt + 1];
          if (nt >= 1) { v0 += dD[4 * nt - 2]; v1 += dD[4 * nt - 1]; }
          if (nt >= 2) { v0 += blo(l4[nt - 2]); v1 += bhi(l4[nt - 2]); }
          if (nt >= 4) { v0 += blo(l8[nt - 4]); v1 += bhi(l8[nt - 4]); }
          o[nt] = cvt2(v0, v1);
        }
        stsm4t(ya, o[0], o[1], o[2], o[3]);
        stsm4t(ya + 512, o[4], o[5], o[6], o[7]);
        fence_async_smem();
        __syncwarp();
        if (lane == 0) {
          asm volatile("cp.async.bulk.global.shared::cta.bulk_group [%0], [%1], 1024;" ::"l"(S->aT + (size_t)(4 * w + c) * 2048 + wq * 512), "r"(ya) : "memory");
          asm volatile("cp.async.bulk.commit_group;" ::: "memory");
        }
      }
    }
    if (lane == 0) asm volatile("cp.async.bulk.wait_group 0;" ::: "memory");
    mbar_wait(bep, 0);
    bar_sync(3, 128);
    if (warp == 12) {
      if (lane == 0) TR(31);
      __syncwarp();
      if (lane < 16) asm volatile("st.relaxed.gpu.global.u32 [%0], %1;" ::"l"(S->flag + ((lane & 15) * 8 + (w >> 4)) * 32 + 16 + (w & 15)), "r"(lds32(sep)) : "memory");
      if (lane == 0) TR(30);
    }
    bar_arrive(0, 160);
  }
}

typedef CUresult (*EncFn)(CUtensorMap*, CUtensorMapDataType, cuuint32_t, void*, const cuuint64_t*, const cuuint64_t*, const cuuint32_t*, const cuuint32_t*,
                          CUtensorMapInterleave, CUtensorMapSwizzle, CUtensorMapL2promotion, CUtensorMapFloatOOBfill);

static void enc(EncFn fn, TMap* out, const void* base, int rank, const cuuint64_t* dims, const cuuint64_t* strides, const cuuint32_t* box,
                CUtensorMapSwizzle sw = CU_TENSOR_MAP_SWIZZLE_128B, CUtensorMapDataType ty = CU_TENSOR_MAP_DATA_TYPE_BFLOAT16) {
  const cuuint32_t es[5] = {1, 1, 1, 1, 1};
  CUtensorMap mp;
  CUresult r = fn(&mp, ty, rank, (void*)base, dims, strides, box, es, CU_TENSOR_MAP_INTERLEAVE_NONE,
                  sw, CU_TENSOR_MAP_L2_PROMOTION_L2_128B, CU_TENSOR_MAP_FLOAT_OOB_FILL_NONE);
  memcpy(out, &mp, 128);
  (void)r;
}

extern "C" void kernel_launch(void* const* d_in, const int* in_sizes, int n_in, void* d_out, int out_size) {
  static EncFn fn = nullptr;
  static Scratch* sp = nullptr;
  static int nsm = 0;
  if (!fn) {
    cudaDriverEntryPointQueryResult qr;
    void* f = nullptr;
    cudaGetDriverEntryPoint("cuTensorMapEncodeTiled", &f, cudaEnableDefault, &qr);
    fn = (EncFn)f;
    cudaGetSymbolAddress((void**)&sp, g_s);
    int dev = 0;
    cudaGetDevice(&dev);
    cudaDeviceGetAttribute(&nsm, cudaDevAttrMultiProcessorCount, dev);
    cudaFuncSetAttribute(fused_kernel<false>, cudaFuncAttributeMaxDynamicSharedMemorySize, SMEM_BYTES);
    cudaFuncSetAttribute(fused_kernel<true>, cudaFuncAttributeMaxDynamicSharedMemorySize, SMEM_BYTES);
  }
  Params p;
  const char* wg = (const char*)d_in[8];
  const char* wu = (const char*)d_in[9];
  const bool swap = wu < wg;
  const char* wbase = swap ? wu : wg;
  const cuuint64_t ms = swap ? (cuuint64_t)(wg - wu) : (cuuint64_t)(wu - wg);
  { cuuint64_t d[4] = {512, 2, 64, 16}, s[3] = {1024, 32768, 2048}; cuuint32_t bx[4] = {64, 2, 4, 16}; enc(fn, &p.x, d_in[0], 4, d, s, bx); bx[3] = 16 / NOUT; enc(fn, &p.out, d_out, 4, d, s, bx); }
  { cuuint64_t d[4] = {64, 512, 28, 2}, s[3] = {3584, 128, ms}; cuuint32_t bx[4] = {64, 32, 2, 2}; enc(fn, &p.wA, wbase, 4, d, s, bx); }
  { cuuint64_t d[4] = {32, 512, 56, 2}, s[3] = {3584, 64, ms}; cuuint32_t bx[4] = {32, 32, 3, 2}; enc(fn, &p.wB, wbase, 4, d, s, bx, CU_TENSOR_MAP_SWIZZLE_64B); }
  { cuuint64_t d[5] = {512, 2, 4, 4, 56}, s[4] = {1024, 8192, 2048, 32768}; cuuint32_t bx[5] = {64, 2, 4, 4, 2}; enc(fn, &p.wd, d_in[10], 5, d, s, bx); }
  { cuuint64_t d[2] = {1792, 2048}, s[1] = {3584}; cuuint32_t bx[2] = {64, 128}; enc(fn, &p.h, sp->h, 2, d, s, bx); }
  { cuuint64_t d[2] = {128, 2048}, s[1] = {1024}; cuuint32_t bx[2] = {UST / 8, 4}; enc(fn, &p.us, sp->uS, 2, d, s, bx, CU_TENSOR_MAP_SWIZZLE_NONE, CU_TENSOR_MAP_DATA_TYPE_UINT64); }
  { cuuint64_t d[3] = {512, 4, 512}, s[2] = {1024, 4096}; cuuint32_t bx[3] = {32, 1, 64}; enc(fn, &p.ut, sp->uS, 3, d, s, bx, CU_TENSOR_MAP_SWIZZLE_NONE); }
  p.u = (const bf16*)d_in[0]; p.logA = (const bf16*)d_in[1]; p.Aim = (const bf16*)d_in[2]; p.Cre = (const bf16*)d_in[3];
  p.Cim = (const bf16*)d_in[4]; p.logdt = (const bf16*)d_in[5]; p.Dsk = (const bf16*)d_in[6]; p.gw = (const bf16*)d_in[11]; p.Wd = (const bf16*)d_in[10];
  p.sc = (uint64_t)sp | (nsm == 132);
  if (swap) fused_kernel<true><<<132, 512, SMEM_BYTES, cudaStreamPerThread>>>(p);
  else fused_kernel<false><<<132, 512, SMEM_BYTES, cudaStreamPerThread>>>(p);
}
```
